```python
import torch

def _softmax(x, axis=-1):
    return torch.softmax(x, dim=axis)

def _gelu(x):
    return torch.nn.functional.gelu(x, approximate='tanh')

def _silu(x):
    return torch.nn.functional.silu(x)

def _sigmoid(x):
    return torch.sigmoid(x)

def _layernorm(x, axis=-1, eps=1e-05):
    m = x.mean(dim=axis, keepdim=True)
    v = x.var(dim=axis, keepdim=True, unbiased=False)
    return (x - m) / torch.sqrt(v + eps)

def _scatter_add(tgt, idx, src, axis=0):
    return tgt.clone().index_add_(axis, idx, src)

def _segment_sum(src, seg, n):
    out = torch.zeros((n,) + src.shape[1:], dtype=src.dtype)
    return out.index_add_(0, seg, src)

def _pad(x, pw):
    flat = tuple((v for pair in reversed(pw) for v in pair))
    return torch.nn.functional.pad(x, flat)
kernel_name = 'adaLN_cond__compressed_kv_cla__dense_activation_gelu__decode'

def setup_inputs():

    _w = lambda a: (lambda t: t.to(torch.bfloat16) if t.is_floating_point() else t)(torch.as_tensor(a))

    def _A_setup():
        B, H, Sq, Sk, D, M = (1, 32, 1, 8192, 128, 512)
        Dc = 4 * D
        return {'x': _w((lambda *s: torch.randn(*s, dtype=torch.bfloat16) * 0.1)(B, Sq, M)), 'c_kv': _w((lambda *s: torch.randn(*s, dtype=torch.bfloat16) * 3.2)(B, Sk, Dc)), 'w_q': _w((lambda *s: torch.randn(*s, dtype=torch.bfloat16) * 0.8)(M, H, D) * M ** (-0.5)), 'w_uk': _w((lambda *s: torch.randn(*s, dtype=torch.bfloat16) * 0.8)(Dc, H, D) * Dc ** (-0.5)), 'w_uv': _w((lambda *s: torch.randn(*s, dtype=torch.bfloat16) * 3.2)(Dc, H, D) * Dc ** (-0.5)), 'w_o': _w((lambda *s: torch.randn(*s, dtype=torch.bfloat16) * 3.2)(H, D, M) * (H * D) ** (-0.5))}
    _A_in = _A_setup()

    def _B_setup():
        B, S, D, F = (1, 1, 512, 1376)
        return {'x': _w((lambda *s: torch.randn(*s, dtype=torch.bfloat16) * 0.1)(B, S, D)), 'w1': _w((lambda *s: torch.randn(*s, dtype=torch.bfloat16) * 3.2)(D, F) * D ** (-0.5)), 'b1': _w((lambda *s: torch.randn(*s, dtype=torch.bfloat16) * 3.2)(F) * 0.01), 'w2': _w((lambda *s: torch.randn(*s, dtype=torch.bfloat16) * 3.2)(F, D) * F ** (-0.5)), 'b2': _w((lambda *s: torch.randn(*s, dtype=torch.bfloat16) * 3.2)(D) * 0.01)}
    _B_in = _B_setup()
    return {'A_x': _A_in['x'], 'A_c_kv': _A_in['c_kv'], 'A_w_q': _A_in['w_q'], 'A_w_uk': _A_in['w_uk'], 'A_w_uv': _A_in['w_uv'], 'A_w_o': _A_in['w_o'], 'B_x': _B_in['x'], 'B_w1': _B_in['w1'], 'B_b1': _B_in['b1'], 'B_w2': _B_in['w2'], 'B_b2': _B_in['b2'], 'c': _w((lambda *s: torch.randn(*s, dtype=torch.bfloat16) * 0.1)(1, 512) * 8.0), 'w_mod': _w((lambda *s: torch.randn(*s, dtype=torch.bfloat16) * 0.1)(512, 6 * 512) * 512 ** (-0.5) * 8.0)}

def reference(A_x, A_c_kv, A_w_q, A_w_uk, A_w_uv, A_w_o, B_x, B_w1, B_b1, B_w2, B_b2, c, w_mod):

    def _A_ref(x, c_kv, w_q, w_uk, w_uv, w_o):
        B, Sq, M = (x.shape[0], x.shape[1], x.shape[2])
        Sk = c_kv.shape[1]
        H, D = (w_q.shape[1], w_q.shape[2])
        q = torch.einsum('bqm,mhd->bhqd', x, w_q)
        k = torch.einsum('bkc,chd->bhkd', c_kv, w_uk)
        v = torch.einsum('bkc,chd->bhkd', c_kv, w_uv)
        scores = torch.einsum('bhqd,bhkd->bhqk', q, k) * D ** (-0.5)
        off = Sk - Sq
        qi = torch.arange(Sq)[:, None]
        kj = torch.arange(Sk)[None, :]
        cmask = kj <= qi + off
        scores = torch.where(cmask[None, None], scores, -1000000000.0)
        p = _softmax(scores, axis=-1)
        ctx = torch.einsum('bhqk,bhkd->bhqd', p, v)
        return torch.einsum('bhqd,hdm->bqm', ctx, w_o)

    def _B_ref(x, w1, b1, w2, b2):
        h = torch.einsum('bsd,df->bsf', x, w1) + b1
        h = _gelu(h)
        return torch.einsum('bsf,fd->bsd', h, w2) + b2
    x = A_x
    mod = (_silu(c) @ w_mod).reshape(c.shape[0], 6, 1, -1)
    sa, ca, ga, sb, cb, gb = (mod[:, 0].clone(), mod[:, 1].clone(), mod[:, 2].clone(), mod[:, 3].clone(), mod[:, 4].clone(), mod[:, 5].clone())
    h = _layernorm(x, axis=-1) * (1 + ca) + sa
    x = x + ga * _A_ref(h, A_c_kv, A_w_q, A_w_uk, A_w_uv, A_w_o)
    h = _layernorm(x, axis=-1) * (1 + cb) + sb
    x = x + gb * _B_ref(h, B_w1, B_b1, B_w2, B_b2)
    return x
```

```cpp
#include <cuda_runtime.h>
#include <cuda_bf16.h>
#include <cuda.h>
#include <stdint.h>

namespace {

constexpr int NCTA = 128;
constexpr int NTHR = 640;
constexpr int NFFN = 43;
constexpr int NMOD = 48;
constexpr int FIN0 = 96;

constexpr int OFF_CKV = 0;
constexpr int OFF_WM2 = OFF_CKV;
constexpr int OFF_W1 = OFF_CKV;
constexpr int OFF_W2 = OFF_CKV + 65536;
constexpr int OFF_WA = 131072;
constexpr int OFF_WB = OFF_WA + 32768;
constexpr int OFF_QA = OFF_WB + 32768;
constexpr int OFF_P = OFF_QA + 16384;
constexpr int OFF_RED = OFF_P + 4096;
constexpr int OFF_SM = OFF_RED + 4096;
constexpr int SM_H = 0;
constexpr int SM_Q = 128;
constexpr int SM_S = 272;
constexpr int SM_STG = 784;
constexpr int SM_MAXA = 848;
constexpr int SM_SUMA = 976;
constexpr int SM_W = 1104;
constexpr int SM_FLAG = 1200;
constexpr int SM_PAR = 1201;
constexpr int SM_MEAN = 1202;
constexpr int SM_PRB = 1204;
constexpr int SM_FLOATS = 1212;
constexpr int OFF_LATE = OFF_CKV + 49152;
constexpr int LT_V = 0;
constexpr int LT_Y = 512;
constexpr int LT_R2 = 2048;
constexpr int LT_ST = 2064;
constexpr int LT_FZ = 2096;
constexpr int OFF_BAR = OFF_SM + SM_FLOATS * 4;
constexpr int NBAR = 40;
constexpr int OFF_TL = OFF_BAR + NBAR * 8;
constexpr int SMEM_BYTES = OFF_TL;
static_assert(SMEM_BYTES <= 232448, "smem");
static_assert(OFF_BAR % 8 == 0, "align");

enum { B_PRB = 0, B_SPARE, B_CA, B_CB0, B_CB1, B_CB2, B_CB3, B_SPARE2, B_SPARE3, B_W1, B_W2, B_EA, B_EB, B_EC, B_H, B_Q,
       B_WO0, B_WUK0 = B_WO0 + 8, B_WUV0 = B_WUK0 + 4, B_WQ0 = B_WUV0 + 4, B_WM0 = B_WQ0 + 4 };

constexpr int A12 = 1024, A13 = 2048, A14 = 4096, A16 = 16384, A17 = 32768, A18 = 65536, A19 = 131072, A20 = 262144;
constexpr int G_EPOCH = A19 + A17;
constexpr int G_X1 = G_EPOCH + 1024;
constexpr int G_X2 = G_X1 + 8 * 1024;
constexpr int G_ML = 0;
constexpr int G_X6 = A18;
constexpr int G_M2 = A20;
constexpr int G_X3 = A13 + A16;
constexpr int G_X5 = A13 + A17;
__host__ __device__ constexpr int gr(int x) { return (x >> 10) * A14 + (x & 1023); }
constexpr int G_X7 = A18 + A20;
constexpr int G_X4 = 524288;
constexpr int G_WORDS = 3 * 524288;
static_assert(G_X2 + 32 * 4 * 128 <= G_EPOCH + A17, "scratch");
__device__ __align__(256) uint32_t g_scratch[G_WORDS + 524288];

constexpr int T_STAG = 161, T_STAG2 = 151, T_STAG3 = 258;
constexpr int T_PI = 85;
constexpr int P_WUK = 2826, P_CA = 5532, P_CB = 8439, P_WUV = 10477, P_WM = 12256, P_WO = 13169, P_W1 = 16053, P_W2 = 17999, P_GB = 18413;
constexpr int S_WQ = 749, I_WQ = 278, S_WUK = 3236, I_WUK = 481, S_CA = 5530, I_CA = 458, S_CB = 6214, I_CB = 47, S_WUV = 10545, I_WUV = 291;
constexpr int S_WM = 12053, I_WM = 280, S_WO = 15346, I_WO = 324, S_W1 = 16987, I_W1 = 202, S_W2 = 18367, I_W2 = 49, S_GB = 19604, I_GB = 71;
constexpr int D_X1 = 846, D_X2 = 289, D_X3 = 447, D_X4 = 885, D_X5 = 1044, D_X6 = 721, D_X8 = 1511;
constexpr int D_WARM = 50, D_WSTEP = 9, D_SB = 625, D_XL = 379;
#define NPROBE 8
#define PRB_NEAR 440u
#define FAST_RANGE 64.f
#define NARROW_PROMO CU_TENSOR_MAP_L2_PROMOTION_NONE

struct Params {
    const __nv_bfloat16 *wmod, *c, *x, *b1, *b2;
    uint32_t* g;
    const __nv_bfloat16 *ckv, *wuk, *wuv, *wo, *w1, *w2;
    __nv_bfloat16* out;
};

constexpr int SPIN_LIMIT = 1 << 22;

__device__ __forceinline__ unsigned clk() { unsigned c; asm volatile("mov.u32 %0, %%clock;" : "=r"(c)); return c; }
__device__ __forceinline__ uint32_t smem_u32(const void* p) { return (uint32_t)__cvta_generic_to_shared(p); }
__device__ __forceinline__ void mbar_init(uint32_t bar, uint32_t cnt) { asm volatile("mbarrier.init.shared::cta.b64 [%0], %1;" :: "r"(bar), "r"(cnt) : "memory"); }
__device__ __forceinline__ void mbar_expect_tx(uint32_t bar, uint32_t bytes) { asm volatile("mbarrier.arrive.expect_tx.shared::cta.b64 _, [%0], %1;" :: "r"(bar), "r"(bytes) : "memory"); }
__device__ __forceinline__ void mbar_arrive(uint32_t bar) { asm volatile("mbarrier.arrive.shared::cta.b64 _, [%0];" :: "r"(bar) : "memory"); }
__device__ __forceinline__ void mbar_wait(uint32_t bar) {
    asm volatile("{ .reg .pred p; .reg .u32 n; mov.u32 n, 0;\n"
                 "LW: mbarrier.try_wait.parity.shared::cta.b64 p, [%0], 0;\n"
                 "@p bra LD;\n add.u32 n, n, 1;\n setp.lt.u32 p, n, 4194304;\n @p bra LW;\n trap;\n LD: }" :: "r"(bar) : "memory");
}
__device__ __forceinline__ bool mbar_test(uint32_t bar) {
    uint32_t ok;
    asm volatile("{ .reg .pred p; mbarrier.test_wait.parity.shared::cta.b64 p, [%1], 0; vote.sync.all.pred p, p, 0xffffffff; selp.u32 %0, 1, 0, p; }" : "=r"(ok) : "r"(bar) : "memory");
    return ok;
}
__device__ __forceinline__ void mbar_arrive_if(uint32_t bar, bool c) {
    asm volatile("{ .reg .pred p; setp.ne.u32 p, %1, 0; @p mbarrier.arrive.shared::cta.b64 _, [%0]; }" :: "r"(bar), "r"((uint32_t)c) : "memory");
}
#define bar_sync(id, n) asm volatile("bar.sync %0, %1;" :: "n"(id), "n"(n) : "memory")
#define bar_arrive(id, n) asm volatile("bar.arrive %0, %1;" :: "n"(id), "n"(n) : "memory")

__device__ __forceinline__ void tma2d(uint32_t dst, const CUtensorMap* m, int c0, int c1, uint32_t bar) {
    asm volatile("{ .reg .pred q; elect.sync _|q, 0xffffffff; @q cp.async.bulk.tensor.2d.shared::cluster.global.mbarrier::complete_tx::bytes [%0], [%1, {%3, %4}], [%2]; }"
                 :: "r"(dst), "l"(m), "r"(bar), "r"(c0), "r"(c1) : "memory");
}
__device__ __forceinline__ void tma2d_mc(uint32_t dst, const CUtensorMap* m, int c0, int c1, uint32_t bar) {
    asm volatile("{ .reg .pred q; elect.sync _|q, 0xffffffff; @q cp.async.bulk.tensor.2d.shared::cluster.global.mbarrier::complete_tx::bytes.multicast::cluster [%0], [%1, {%3, %4}], [%2], %5; }"
                 :: "r"(dst), "l"(m), "r"(bar), "r"(c0), "r"(c1), "h"((uint16_t)3) : "memory");
}
__device__ __forceinline__ void tma3d(uint32_t dst, const CUtensorMap* m, int c0, int c1, int c2, uint32_t bar) {
    asm volatile("{ .reg .pred q; elect.sync _|q, 0xffffffff; @q cp.async.bulk.tensor.3d.shared::cluster.global.mbarrier::complete_tx::bytes [%0], [%1, {%3, %4, %5}], [%2]; }"
                 :: "r"(dst), "l"(m), "r"(bar), "r"(c0), "r"(c1), "r"(c2) : "memory");
}

__device__ __forceinline__ void pf_lin(const void* src, uint32_t bytes) {
    asm volatile("cp.async.bulk.prefetch.L2.global [%0], %1;" :: "l"(src), "r"(bytes) : "memory");
}

__device__ __forceinline__ uint32_t ldx32(const void* p) { uint32_t v; asm volatile("ld.relaxed.gpu.global.u32 %0, [%1];" : "=r"(v) : "l"(p) : "memory"); return v; }
__device__ __forceinline__ uint2 ldx64(const void* p) { uint2 v; asm volatile("ld.relaxed.gpu.global.v2.u32 {%0,%1}, [%2];" : "=r"(v.x), "=r"(v.y) : "l"(p) : "memory"); return v; }
__device__ __forceinline__ uint4 ldx128(const void* p) { uint4 v; asm volatile("ld.relaxed.gpu.global.v4.u32 {%0,%1,%2,%3}, [%4];" : "=r"(v.x), "=r"(v.y), "=r"(v.z), "=r"(v.w) : "l"(p) : "memory"); return v; }
__device__ __forceinline__ void stx32(void* p, uint32_t v) { asm volatile("st.relaxed.gpu.global.u32 [%0], %1;" :: "l"(p), "r"(v) : "memory"); }
__device__ __forceinline__ void stx64(void* p, uint32_t a, uint32_t b) { asm volatile("st.relaxed.gpu.global.v2.u32 [%0], {%1,%2};" :: "l"(p), "r"(a), "r"(b) : "memory"); }
__device__ __forceinline__ void stx128(void* p, uint32_t a, uint32_t b, uint32_t c, uint32_t d) { asm volatile("st.relaxed.gpu.global.v4.u32 [%0], {%1,%2,%3,%4};" :: "l"(p), "r"(a), "r"(b), "r"(c), "r"(d) : "memory"); }
__device__ __forceinline__ void ldx32_if(uint32_t& v, const void* p, bool c) { asm volatile("{ .reg .pred q; setp.ne.u32 q, %2, 0; @q ld.relaxed.gpu.global.u32 %0, [%1]; }" : "+r"(v) : "l"(p), "r"((uint32_t)c) : "memory"); }
__device__ __forceinline__ void ldx64_if(uint2& v, const void* p, bool c) { asm volatile("{ .reg .pred q; setp.ne.u32 q, %3, 0; @q ld.relaxed.gpu.global.v2.u32 {%0,%1}, [%2]; }" : "+r"(v.x), "+r"(v.y) : "l"(p), "r"((uint32_t)c) : "memory"); }
__device__ __forceinline__ void ldx128_if(uint4& v, const void* p, bool c) { asm volatile("{ .reg .pred q; setp.ne.u32 q, %5, 0; @q ld.relaxed.gpu.global.v4.u32 {%0,%1,%2,%3}, [%4]; }" : "+r"(v.x), "+r"(v.y), "+r"(v.z), "+r"(v.w) : "l"(p), "r"((uint32_t)c) : "memory"); }
__device__ __forceinline__ void stx32_if(void* p, uint32_t v, bool c) { asm volatile("{ .reg .pred q; setp.ne.u32 q, %2, 0; @q st.relaxed.gpu.global.u32 [%0], %1; }" :: "l"(p), "r"(v), "r"((uint32_t)c) : "memory"); }
__device__ __forceinline__ void stx64_if(void* p, uint32_t a, uint32_t b, bool c) { asm volatile("{ .reg .pred q; setp.ne.u32 q, %3, 0; @q st.relaxed.gpu.global.v2.u32 [%0], {%1,%2}; }" :: "l"(p), "r"(a), "r"(b), "r"((uint32_t)c) : "memory"); }
__device__ __forceinline__ void stx128_if(void* p, uint32_t a, uint32_t b, uint32_t c, uint32_t d, bool e) { asm volatile("{ .reg .pred q; setp.ne.u32 q, %5, 0; @q st.relaxed.gpu.global.v4.u32 [%0], {%1,%2,%3,%4}; }" :: "l"(p), "r"(a), "r"(b), "r"(c), "r"(d), "r"((uint32_t)e) : "memory"); }
__device__ __forceinline__ void sts16_if(uint32_t a, uint32_t v, bool c) { asm volatile("{ .reg .pred q; .reg .b16 h; setp.ne.u32 q, %2, 0; cvt.u16.u32 h, %1; @q st.shared.u16 [%0], h; }" :: "r"(a), "r"(v), "r"((uint32_t)c) : "memory"); }
__device__ __forceinline__ void sts32_if(uint32_t a, float v, bool c) { asm volatile("{ .reg .pred q; setp.ne.u32 q, %2, 0; @q st.shared.f32 [%0], %1; }" :: "r"(a), "f"(v), "r"((uint32_t)c) : "memory"); }
__device__ __forceinline__ void sts64_if(uint32_t a, float v, float u, bool c) { asm volatile("{ .reg .pred q; setp.ne.u32 q, %3, 0; @q st.shared.v2.f32 [%0], {%1,%2}; }" :: "r"(a), "f"(v), "f"(u), "r"((uint32_t)c) : "memory"); }
__device__ __forceinline__ void spin_guard(int& it) { if (++it > SPIN_LIMIT) __trap(); }
__device__ __forceinline__ void delay(int cyc) { if (cyc > 0) { const unsigned a = clk(); while ((int)(clk() - a) < cyc) { } } }
__device__ __forceinline__ uint32_t tagu(uint32_t w, uint32_t par) { uint32_t r; asm("lop3.b32 %0, %1, 0xfffffffe, %2, 0xEA;" : "=r"(r) : "r"(w), "r"(par)); return r; }
__device__ __forceinline__ uint32_t tagf(float f, uint32_t par) { return tagu(__float_as_uint(f), par); }
__device__ __forceinline__ bool bad(uint32_t w, uint32_t par) { return (w ^ par) & 1u; }
__device__ __forceinline__ uint32_t mis2(uint32_t a, uint32_t b, uint32_t par) { uint32_t r; asm("lop3.b32 %0, %1, %2, %3, 0x7E;" : "=r"(r) : "r"(a), "r"(b), "r"(par)); return r; }
__device__ __forceinline__ uint32_t or3(uint32_t a, uint32_t b, uint32_t c) { uint32_t r; asm volatile("lop3.b32 %0, %1, %2, %3, 0xFE;" : "=r"(r) : "r"(a), "r"(b), "r"(c)); return r; }
__device__ __forceinline__ bool any_bit0(uint32_t m) { return __any_sync(0xffffffffu, m & 1u); }
__device__ __forceinline__ uint4 ldv(const void* p) {
    uint4 v; asm volatile("{ .reg .b128 t; .reg .b64 a, b; ld.relaxed.gpu.global.b128 t, [%4]; mov.b128 {a, b}, t; mov.b64 {%0,%1}, a; mov.b64 {%2,%3}, b; }"
                          : "=r"(v.x), "=r"(v.y), "=r"(v.z), "=r"(v.w) : "l"(p) : "memory"); return v;
}
__device__ __forceinline__ void ldv_if(uint4& v, const void* p, bool c) {
    asm volatile("{ .reg .pred q; .reg .b128 t; .reg .b64 a, b; setp.ne.u32 q, %5, 0; mov.b64 a, {%0,%1}; mov.b64 b, {%2,%3}; mov.b128 t, {a, b};\n"
                 "@q ld.relaxed.gpu.global.b128 t, [%4]; mov.b128 {a, b}, t; mov.b64 {%0,%1}, a; mov.b64 {%2,%3}, b; }"
                 : "+r"(v.x), "+r"(v.y), "+r"(v.z), "+r"(v.w) : "l"(p), "r"((uint32_t)c) : "memory");
}
__device__ __forceinline__ void stv_if(void* p, uint32_t x, uint32_t y, uint32_t z, uint32_t w, bool c) {
    asm volatile("{ .reg .pred q; .reg .b128 t; .reg .b64 a, b; setp.ne.u32 q, %5, 0; mov.b64 a, {%1,%2}; mov.b64 b, {%3,%4}; mov.b128 t, {a, b};\n"
                 "@q st.relaxed.gpu.global.b128 [%0], t; }" :: "l"(p), "r"(x), "r"(y), "r"(z), "r"(w), "r"((uint32_t)c) : "memory");
}
__device__ __forceinline__ void stp_if(void* p, uint32_t x, uint32_t y, bool c) {
    asm volatile("{ .reg .pred q; .reg .b64 a; setp.ne.u32 q, %3, 0; mov.b64 a, {%1,%2}; @q st.relaxed.gpu.global.b64 [%0], a; }" :: "l"(p), "r"(x), "r"(y), "r"((uint32_t)c) : "memory");
}
__device__ __forceinline__ uint2 ldp(const void* p) {
    uint2 v; asm volatile("{ .reg .b64 a; ld.relaxed.gpu.global.b64 a, [%2]; mov.b64 {%0,%1}, a; }" : "=r"(v.x), "=r"(v.y) : "l"(p) : "memory"); return v;
}
__device__ __forceinline__ void ldp_if(uint2& v, const void* p, bool c) {
    asm volatile("{ .reg .pred q; .reg .b64 a; setp.ne.u32 q, %3, 0; mov.b64 a, {%0,%1}; @q ld.relaxed.gpu.global.b64 a, [%2]; mov.b64 {%0,%1}, a; }" : "+r"(v.x), "+r"(v.y) : "l"(p), "r"((uint32_t)c) : "memory");
}
__device__ __forceinline__ uint32_t* inbox(uint32_t* G, int c, uint32_t k, int x) {
    return G + G_X4 + (c & 1) * A13 + (c >> 1) * A16 + ((k ^ __popc(c & 0x17)) & 1u) * A12 + gr(x);
}
#define PIN(x) asm volatile("" : "+r"(x))
#define PINP(x) asm volatile("" : "+l"(x))

__device__ __forceinline__ float bf_lo(uint32_t w) { return __uint_as_float(w << 16); }
__device__ __forceinline__ float bf_hi(uint32_t w) { return __uint_as_float(w & 0xffff0000u); }
__device__ __forceinline__ uint32_t pack_bf(float lo, float hi) { uint32_t r; asm("cvt.rn.bf16x2.f32 %0, %1, %2;" : "=r"(r) : "f"(hi), "f"(lo)); return r; }
__device__ __forceinline__ float rbf(float v) { return __uint_as_float(pack_bf(0.f, v)); }
__device__ __forceinline__ float ex2(float x) { float y; asm("ex2.approx.ftz.f32 %0, %1;" : "=f"(y) : "f"(x)); return y; }
__device__ __forceinline__ float rcp(float x) { float y; asm("rcp.approx.ftz.f32 %0, %1;" : "=f"(y) : "f"(x)); return y; }
__device__ __forceinline__ float rsq(float x) { float y; asm("rsqrt.approx.ftz.f32 %0, %1;" : "=f"(y) : "f"(x)); return y; }
__device__ __forceinline__ float sigmoidf_(float x) { return rcp(1.f + ex2(-1.4426950408889634f * x)); }
__device__ __forceinline__ uint32_t ldg16(const void* p) { uint32_t v; asm volatile("ld.global.nc.u16 %0, [%1];" : "=r"(v) : "l"(p)); return v; }
__device__ __forceinline__ uint4 ldg128(const void* p) { uint4 v; asm volatile("ld.global.nc.v4.u32 {%0,%1,%2,%3}, [%4];" : "=r"(v.x), "=r"(v.y), "=r"(v.z), "=r"(v.w) : "l"(p)); return v; }
__device__ __forceinline__ uint32_t ldg32(const void* p) { uint32_t v; asm volatile("ld.global.nc.u32 %0, [%1];" : "=r"(v) : "l"(p)); return v; }
__device__ __forceinline__ uint2 ldg64(const void* p) { uint2 v; asm volatile("ld.global.nc.v2.u32 {%0,%1}, [%2];" : "=r"(v.x), "=r"(v.y) : "l"(p)); return v; }

__device__ __forceinline__ uint32_t gdesc(uint32_t addr) { return ((addr & 0x3FFFF) >> 4) | (1u << 16); }
template <int TRANS_A, int ACC>
__device__ __forceinline__ void wgmma16(float (&d)[8], uint32_t da, uint32_t db) {
    asm volatile("{ .reg .b64 a, b; mov.b64 a, {%8, %12}; mov.b64 b, {%9, %12};\n"
                 "wgmma.mma_async.sync.aligned.m64n16k16.f32.bf16.bf16 {%0,%1,%2,%3,%4,%5,%6,%7}, a, b, %10, 1, 1, %11, 0; }"
                 : "+f"(d[0]), "+f"(d[1]), "+f"(d[2]), "+f"(d[3]), "+f"(d[4]), "+f"(d[5]), "+f"(d[6]), "+f"(d[7])
                 : "r"(da), "r"(db), "n"(ACC), "n"(TRANS_A), "n"(0x40000040));
}
__device__ __forceinline__ void wg_fence() { asm volatile("wgmma.fence.sync.aligned;" ::: "memory"); }
__device__ __forceinline__ void wg_commit() { asm volatile("wgmma.commit_group.sync.aligned;" ::: "memory"); }
__device__ __forceinline__ void wg_wait0() { asm volatile("wgmma.wait_group.sync.aligned 0;" ::: "memory"); }
__device__ __forceinline__ void fence_async() { asm volatile("fence.proxy.async.shared::cta;" ::: "memory"); }

__device__ __forceinline__ uint32_t lds32(uint32_t a) { uint32_t v; asm volatile("ld.shared.u32 %0, [%1];" : "=r"(v) : "r"(a) : "memory"); return v; }
__device__ __forceinline__ float ldsf(uint32_t a) { float v; asm volatile("ld.shared.f32 %0, [%1];" : "=f"(v) : "r"(a) : "memory"); return v; }
__device__ __forceinline__ float4 ldsf4(uint32_t a) { float4 v; asm volatile("ld.shared.v4.f32 {%0,%1,%2,%3}, [%4];" : "=f"(v.x), "=f"(v.y), "=f"(v.z), "=f"(v.w) : "r"(a) : "memory"); return v; }
__device__ __forceinline__ uint4 lds128(uint32_t a) { uint4 v; asm volatile("ld.shared.v4.u32 {%0,%1,%2,%3}, [%4];" : "=r"(v.x), "=r"(v.y), "=r"(v.z), "=r"(v.w) : "r"(a) : "memory"); return v; }
__device__ __forceinline__ float sum4(const float4& v) { return (v.x + v.y) + (v.z + v.w); }
template <int N, int STRIDE>
__device__ __forceinline__ void load_cols(float (&wv)[32], uint32_t addr) {
    uint32_t raw[N];
#pragma unroll
    for (int i = 0; i < N; i++) raw[i] = lds32(addr + i * STRIDE);
#pragma unroll
    for (int i = 0; i < N; i++) { wv[2 * i] = bf_lo(raw[i]); wv[2 * i + 1] = bf_hi(raw[i]); }
}
__device__ __forceinline__ void keep32(const float (&wv)[32], uint32_t addr, uint32_t never) {
#pragma unroll
    for (int i = 0; i < 32; i += 4)
        asm volatile("{ .reg .pred q; setp.ne.u32 q, %5, 0; @q st.shared.v4.f32 [%0], {%1,%2,%3,%4}; }" :: "r"(addr), "f"(wv[i]), "f"(wv[i + 1]), "f"(wv[i + 2]), "f"(wv[i + 3]), "r"(never) : "memory");
}
template <int N>
__device__ __forceinline__ float2 dot_cols(const float (&wv)[32], uint32_t vaddr) {
    float a0 = 0.f, a1 = 0.f, b0 = 0.f, b1 = 0.f;
#pragma unroll
    for (int q = 0; q < N / 4; q++) {
        const float4 v = ldsf4(vaddr + 16 * q);
        a0 = fmaf(v.x, wv[8 * q], a0); b0 = fmaf(v.x, wv[8 * q + 1], b0); a1 = fmaf(v.y, wv[8 * q + 2], a1); b1 = fmaf(v.y, wv[8 * q + 3], b1);
        a0 = fmaf(v.z, wv[8 * q + 4], a0); b0 = fmaf(v.z, wv[8 * q + 5], b0); a1 = fmaf(v.w, wv[8 * q + 6], a1); b1 = fmaf(v.w, wv[8 * q + 7], b1);
    }
    return make_float2(a0 + a1, b0 + b1);
}
__device__ __forceinline__ float reduce16(const float2& y, int l) {
    float r = ((l & 16) ? y.y : y.x) + __shfl_xor_sync(0xffffffffu, (l & 16) ? y.x : y.y, 16);
    return r + __shfl_xor_sync(0xffffffffu, r, 8);
}

__global__ void __cluster_dims__(2, 1, 1) __launch_bounds__(NTHR, 1)
fused_decode_kernel(const Params p, const __grid_constant__ CUtensorMap m_wq, const __grid_constant__ CUtensorMap m_wuk,
                    const __grid_constant__ CUtensorMap m_ckv, const __grid_constant__ CUtensorMap m_wuv,
                    const __grid_constant__ CUtensorMap m_wo, const __grid_constant__ CUtensorMap m_wm,
                    const __grid_constant__ CUtensorMap m_w1, const __grid_constant__ CUtensorMap m_w2, const __grid_constant__ CUtensorMap m_gb) {
    extern __shared__ __align__(1024) unsigned char smem[];
    const unsigned t0 = clk();
    const int t = threadIdx.x, l = t & 31;
    const int w = __shfl_sync(0xffffffffu, t >> 5, 0);
    const int cta = blockIdx.x;
    const uint32_t sb = smem_u32(smem);
    const uint32_t bars = sb + OFF_BAR;
    float* sm = reinterpret_cast<float*>(smem + OFF_SM);
    const int hd = cta >> 2, js = cta & 3;
    const int grp = cta & 1, split = cta >> 1;

    uint32_t* const G = p.g;
    const int ph = (cta * T_STAG) >> 7;
#define AT(s, i) while ((int)(clk() - t0) < S_##s + (i) * I_##s + ph) { __nanosleep(32); }
#define AT2(s, i, st) while ((int)(clk() - t0) < S_##s + (i) * I_##s + ((cta * st) >> 7)) { __nanosleep(32); }
    if (w >= 18) {
        const int u = t - 576;
        asm volatile("barrier.cluster.arrive.relaxed.aligned;" ::: "memory");
        delay(D_XL);
        const uint4 xa = ldg128(p.x + 8 * l), xb = ldg128(p.x + 256 + 8 * l);
        const uint32_t x_sl = ldg32(p.x + 128 * js + 2 * u);
        float ln0, ln1;
        {
            float e[16] = {bf_lo(xa.x), bf_hi(xa.x), bf_lo(xa.y), bf_hi(xa.y), bf_lo(xa.z), bf_hi(xa.z), bf_lo(xa.w), bf_hi(xa.w),
                           bf_lo(xb.x), bf_hi(xb.x), bf_lo(xb.y), bf_hi(xb.y), bf_lo(xb.z), bf_hi(xb.z), bf_lo(xb.w), bf_hi(xb.w)};
            float sx = 0.f;
#pragma unroll
            for (int i = 0; i < 16; i++) sx += e[i];
#pragma unroll
            for (int o = 16; o; o >>= 1) sx += __shfl_xor_sync(0xffffffffu, sx, o);
            const float mean = sx * (1.f / 512.f);
            float q = 0.f;
#pragma unroll
            for (int i = 0; i < 16; i++) q += (e[i] - mean) * (e[i] - mean);
#pragma unroll
            for (int o = 16; o; o >>= 1) q += __shfl_xor_sync(0xffffffffu, q, o);
            const float den = rbf(sqrtf(rbf(rbf(q * (1.f / 512.f)) + 1e-5f))), mb = rbf(mean);
            ln0 = rbf(__fdividef(rbf(bf_lo(x_sl) - mb), den)); ln1 = rbf(__fdividef(rbf(bf_hi(x_sl) - mb), den));
            sts32_if(sb + OFF_SM + SM_MEAN * 4, mean, u == 0);
        }
        asm volatile("barrier.cluster.wait.aligned;" ::: "memory");
        const uint32_t* x1src = G + G_X1 + 128 * js + 2 * u;
        const uint32_t* x2src = G + G_X2 + hd * 512 + 2 * u;
        PINP(x1src); PINP(x2src);
        bar_sync(5, 128);
        uint32_t par = __float_as_uint(sm[SM_PAR]);
        PIN(par);
        int it = 0;
        {
            uint2 v[16];
            delay(D_X1);
#pragma unroll
            for (int i = 0; i < 16; i++) v[i] = ldx64(x1src + i * 512);
            while (true) {
                uint32_t m[16];
#pragma unroll
                for (int i = 0; i < 16; i++) m[i] = mis2(v[i].x, v[i].y, par);
                if (!any_bit0(or3(or3(or3(m[0], m[1], m[2]), or3(m[3], m[4], m[5]), or3(m[6], m[7], m[8])), or3(or3(m[9], m[10], m[11]), or3(m[12], m[13], m[14]), m[15]), 0u))) break;
#pragma unroll
                for (int i = 0; i < 16; i++) ldx64_if(v[i], x1src + i * 512, mis2(v[i].x, v[i].y, par) & 1u);
                spin_guard(it);
            }
            float sa0 = 0.f, sa1 = 0.f, ca0 = 0.f, ca1 = 0.f;
#pragma unroll
            for (int i = 0; i < 16; i += 2) { sa0 += __uint_as_float(v[i].x); sa1 += __uint_as_float(v[i].y); ca0 += __uint_as_float(v[i + 1].x); ca1 += __uint_as_float(v[i + 1].y); }
            sts64_if(sb + OFF_SM + (SM_H + 2 * u) * 4, rbf(rbf(ln0 * rbf(1.f + rbf(ca0))) + rbf(sa0)), rbf(rbf(ln1 * rbf(1.f + rbf(ca1))) + rbf(sa1)), true);
            __syncwarp();
            mbar_arrive_if(bars + 8 * B_H, l == 0);
        }
        {
            bar_sync(9, 192);
            delay(D_X2);
            uint2 a0 = ldx64(x2src), a1 = ldx64(x2src + 128), a2 = ldx64(x2src + 256), a3 = ldx64(x2src + 384);
            while (any_bit0(or3(or3(mis2(a0.x, a0.y, par), mis2(a1.x, a1.y, par), mis2(a2.x, a2.y, par)), mis2(a3.x, a3.y, par), 0u))) {
                ldx64_if(a0, x2src, mis2(a0.x, a0.y, par) & 1u); ldx64_if(a1, x2src + 128, mis2(a1.x, a1.y, par) & 1u);
                ldx64_if(a2, x2src + 256, mis2(a2.x, a2.y, par) & 1u); ldx64_if(a3, x2src + 384, mis2(a3.x, a3.y, par) & 1u);
                spin_guard(it);
            }
            sts64_if(sb + OFF_SM + (SM_Q + 2 * u + (u >> 4) * 4) * 4, rbf((__uint_as_float(a0.x) + __uint_as_float(a1.x)) + (__uint_as_float(a2.x) + __uint_as_float(a3.x))),
                     rbf((__uint_as_float(a0.y) + __uint_as_float(a1.y)) + (__uint_as_float(a2.y) + __uint_as_float(a3.y))), true);
            __syncwarp();
            mbar_arrive_if(bars + 8 * B_Q, l == 0);
        }
        if (w == 18) {
            {
                bar_sync(3, 544);
                const float ref = sm[SM_W + (l >> 1)];
                const float2 ls = *reinterpret_cast<const float2*>(sm + SM_W + 16 + 2 * l);
                float M = ref;
                if (__any_sync(0xffffffffu, ref != 0.f)) {
#pragma unroll
                    for (int o = 16; o > 1; o >>= 1) M = fmaxf(M, __shfl_xor_sync(0xffffffffu, M, o));
                }
                float L = (ls.x + ls.y) * ex2(ref - M);
#pragma unroll
                for (int o = 16; o; o >>= 1) L += __shfl_xor_sync(0xffffffffu, L, o);
                sts32_if(sb + OFF_SM + (SM_W + 80) * 4, rcp(L), l == 0);
                bar_arrive(8, 544);
            }
            const uint32_t lt = sb + OFF_LATE;
            if (cta < NFFN) {
                uint32_t* x7dst = G + G_X7 + gr(32 * cta + l);
                uint32_t fr = lt + (LT_FZ + l * 20) * 4, s0 = lt + (LT_ST + (l >> 4) * 16) * 4;
                const float b1v = bf_lo(ldg16(p.b1 + 32 * cta + l));
                PINP(x7dst); PIN(fr); PIN(s0);
                bar_sync(7, 544);
                const float tu = (sum4(ldsf4(fr + 2560)) + sum4(ldsf4(fr + 2576))) + (sum4(ldsf4(fr + 2592)) + sum4(ldsf4(fr + 2608)));
                float tv = (sum4(ldsf4(fr + 5120)) + sum4(ldsf4(fr + 5136))) + (sum4(ldsf4(fr + 5152)) + sum4(ldsf4(fr + 5168))) + b1v;
                sts64_if(sb, tu, tv, par >> 1);
                bar_sync(14, 544);

                const float st = (sum4(ldsf4(s0)) + sum4(ldsf4(s0 + 16))) + (sum4(ldsf4(s0 + 32)) + sum4(ldsf4(s0 + 48)));
                const float tz = (sum4(ldsf4(fr)) + sum4(ldsf4(fr + 16))) + (sum4(ldsf4(fr + 32)) + sum4(ldsf4(fr + 48)));
                const float so = __shfl_xor_sync(0xffffffffu, st, 16);
                const float mu = ((l & 16) ? so : st) * (1.f / 512.f);
                const float z = (tz - mu * tu) * rsq(fmaxf(((l & 16) ? st : so) * (1.f / 512.f) - mu * mu, 0.f) + 1e-5f) + tv;
                const uint32_t hz = tagf(z * rcp(1.f + ex2(z * fmaf(z * z, -0.10294324f, -2.3022082f))), par);
                stx32(x7dst, hz); stx32(x7dst + A12, hz);
            } else if (cta < NFFN + NMOD) {
                uint32_t* dst = G + G_M2 + gr(32 * (cta - NFFN) + l);
                const uint32_t fr = lt + (LT_FZ + l * 20) * 4;
                bar_sync(7, 544);
                const uint32_t r = tagf(rbf((sum4(ldsf4(fr)) + sum4(ldsf4(fr + 16))) + (sum4(ldsf4(fr + 32)) + sum4(ldsf4(fr + 48)))), par);
                stx32(dst, r); stx32(dst + A12, r);
            } else if (cta >= FIN0) {
                const uint32_t va = sb + OFF_SM + (SM_S + 16 * (l >> 3)) * 4;
                float a0 = 0.f, a1 = 0.f, b0 = 0.f, b1 = 0.f;
#pragma unroll 1
                for (int b = 0; b < 4; b++) {
                    float4 v[8];
#pragma unroll
                    for (int q = 0; q < 8; q++) v[q] = ldsf4(va + 512 * b + 256 * (q >> 2) + 16 * (q & 3));
                    mbar_wait(bars + 8 * (B_WM0 + b));
                    uint32_t raw[32];
#pragma unroll
                    for (int i = 0; i < 32; i++) raw[i] = lds32(sb + OFF_WM2 + b * 4096 + i * 128 + l * 4);
#pragma unroll
                    for (int q = 0; q < 8; q++) {
                        a0 = fmaf(v[q].x, bf_lo(raw[4 * q]), a0); b0 = fmaf(v[q].x, bf_hi(raw[4 * q]), b0); a1 = fmaf(v[q].y, bf_lo(raw[4 * q + 1]), a1); b1 = fmaf(v[q].y, bf_hi(raw[4 * q + 1]), b1);
                        a0 = fmaf(v[q].z, bf_lo(raw[4 * q + 2]), a0); b0 = fmaf(v[q].z, bf_hi(raw[4 * q + 2]), b0); a1 = fmaf(v[q].w, bf_lo(raw[4 * q + 3]), a1); b1 = fmaf(v[q].w, bf_hi(raw[4 * q + 3]), b1);
                    }
                }
                sts32_if(lt + (LT_R2 + 2 * (l & 7) + (l >> 4)) * 4, rbf(reduce16(make_float2(a0 + a1, b0 + b1), l)), !(l & 8));
                bar_arrive(4, 544);
            }
        }
        if (w == 19) {
            mbar_wait(bars + 8 * B_EA);
#pragma unroll 1
            for (int i = 0; i < 8; i++) { AT(WUV, i); tma3d(sb + OFF_WA + i * 4096, &m_wuv, hd * 128, (js & 1) * 32 + (i & 1) * 16, (js >> 1) * 4 + (i >> 1), bars + 8 * (B_WUV0 + (i >> 1))); }

            mbar_wait(bars + 8 * B_EC);
            if (cta < NFFN) {
#pragma unroll 1
                for (int i = 0; i < 8; i++) { AT2(W1, i, T_STAG3); tma2d(sb + OFF_W1 + i * 4096, &m_w1, 32 * cta, 64 * i, bars + 8 * B_W1); }
            } else if (cta < NFFN + NMOD) {
#pragma unroll 1
                for (int i = 0; i < 8; i++) { AT(WM, i); tma2d(sb + OFF_WM2 + i * 4096, &m_wm, 1024 + 32 * (cta - NFFN), 64 * i, bars + 8 * (B_WM0 + (i >> 1))); }
            } else if (cta >= FIN0) {
#pragma unroll 1
                for (int i = 0; i < 11; i++) { AT(W2, i); tma2d(sb + OFF_W2 + i * 4096, &m_w2, 16 * (cta - FIN0), 128 * i, bars + 8 * B_W2); }
#pragma unroll 1
                for (int i = 0; i < 4; i++) { AT(GB, i); tma2d(sb + OFF_WM2 + i * 4096, &m_gb, 1024 + 16 * cta, 128 * i, bars + 8 * (B_WM0 + i)); }
            }
        }
        __syncwarp();
        return;
    }
    if (w >= 16) {
        if (w == 17) {
            asm volatile("barrier.cluster.arrive.relaxed.aligned;" ::: "memory");
            const __nv_bfloat16* src = p.x; int step = 0, bytes = 128, left = 0, next = 0;
            if (l == 0) { src = p.wuk + (size_t)(128 * (cta >> 5) + (cta & 31)) * 4096; step = 32 * 4096; bytes = 8192; left = 4; next = P_WUK; }
            if (l == 1) { src = p.ckv + (size_t)(split * 128 + grp * 8) * 512; step = 16 * 512; bytes = 8192; left = 4; next = P_CA; }
            if (l == 2) { src = p.ckv + (size_t)(split * 128 + 64 + grp * 8) * 512; step = 16 * 512; bytes = 8192; left = 4; next = P_CB; }
            if (l == 3) { src = p.wuv + (size_t)(256 * (cta >> 6) + (cta & 63)) * 4096; step = 64 * 4096; bytes = 8192; left = 4; next = P_WUV; }
            if (l == 4) { src = p.wmod + (size_t)cta * 3072 + 1024; step = 128 * 3072; bytes = 3072; left = 4; next = P_WM; }
            if (l == 5) { src = p.wo + (size_t)((cta >> 4) * 512 + (cta & 15) * 8) * 512; step = 128 * 512; bytes = 8192; left = 4; next = P_WO; }
            if (l == 6) { src = p.w1 + (size_t)(cta * 2) * 1376; step = 256 * 1376; bytes = 5504; left = 2; next = P_W1; }
            if (l == 7) { src = p.w2 + (size_t)cta * 5504; step = 2752; bytes = 5504; left = 2; next = P_W2; }
            if (l == 8) { src = p.wmod + (size_t)cta * 3072 + 2560; step = 128 * 3072; bytes = 1024; left = 4; next = P_GB; }
            if (l == 9 && cta < 38) { src = cta < 8 ? p.x + 64 * cta : (cta < 16 ? p.b2 + 64 * (cta - 8) : p.b1 + 64 * (cta - 16)); bytes = cta == 37 ? 64 : 128; left = 1; next = -ph; }
            const int gap = (bytes * T_PI) >> 10;
            next += ph;
            while (__any_sync(0xffffffffu, left > 0)) {
                const int now = (int)(clk() - t0);
                if (left > 0 && now >= next) { pf_lin(src, bytes); src += step; next += gap; left--; }
                __syncwarp();
                __nanosleep(32);
            }
            asm volatile("barrier.cluster.wait.aligned;" ::: "memory");
            return;
        }
        if (l == 0) {
#pragma unroll
            for (int i = 0; i < 4; i++) mbar_init(bars + 8 * (B_WQ0 + i), 1);
            asm volatile("fence.mbarrier_init.release.cluster;" ::: "memory");
#pragma unroll
            for (int i = 0; i < 4; i++) mbar_expect_tx(bars + 8 * (B_WQ0 + i), 8192);
        }
        __syncwarp();
        asm volatile("barrier.cluster.arrive.relaxed.aligned;" ::: "memory");
        {
#pragma unroll 1
            for (int i = 0; i < 8; i++) { AT(WQ, i); tma2d(sb + OFF_WA + i * 4096, &m_wq, hd * 128, js * 128 + i * 16, bars + 8 * (B_WQ0 + (i >> 1))); }
        }
        __syncwarp();
        asm volatile("barrier.cluster.wait.aligned;" ::: "memory");
        {
#pragma unroll 1
            for (int i = 0; i < 8; i++) { AT(WUK, i); tma2d(sb + OFF_WB + (i & 1) * 16384 + (i >> 1) * 4096, &m_wuk, hd * 128 + (i & 1) * 64, js * 128 + (i >> 1) * 32, bars + 8 * (B_WUK0 + (i >> 1))); }

#pragma unroll 1
            for (int i = 0; i < 16; i++) {
                const int ch = i >> 3, cb = 2 * ((i >> 1) & 3) + grp, kh = i & 1;
                if (ch == 0) { AT(CA, i); } else { AT2(CB, i - 8, T_STAG3); }
                tma2d_mc(sb + OFF_CKV + ch * 65536 + cb * 8192 + kh * 4096, &m_ckv, cb * 64, split * 128 + ch * 64 + kh * 32, bars + 8 * (ch == 0 ? B_CA : B_CB0 + ((i >> 1) & 3)));
            }

            mbar_wait(bars + 8 * B_EB);
#pragma unroll 1
            for (int i = 0; i < 8; i++) { AT2(WO, i, T_STAG2); tma2d(sb + OFF_WB + i * 4096, &m_wo, (cta & 15) * 32, (cta >> 4) * 512 + i * 64, bars + 8 * (B_WO0 + i)); }
        }
        __syncwarp();
        return;
    }

    uint4 wm0;
    {
        const __nv_bfloat16* src = p.wmod + (size_t)(64 * (cta >> 4) + (t >> 3)) * 3072 + 64 * (cta & 15) + 8 * (t & 7);
        asm volatile("ld.global.nc.L1::no_allocate.v4.u32 {%0,%1,%2,%3}, [%4];" : "=r"(wm0.x), "=r"(wm0.y), "=r"(wm0.z), "=r"(wm0.w) : "l"(src));
    }
    const uint32_t c_row_r = ldg16(p.c + 64 * (cta >> 4) + (t >> 3));
    const int x5own = G_X5 + (js & 1) * A18 + (js >> 1) * A20 + gr(hd * 128);
    uint32_t epoch_r = 0;
    ldx32_if(epoch_r, G + G_EPOCH + (cta & 31) * 32, w < 2);
    if (l == 0) {
        mbar_init(bars + 8 * w, w == B_EC ? 8 : (w >= B_H ? 2 : (w == B_PRB ? 4 : 1)));
        mbar_init(bars + 8 * (w + 16), 1);
        if (w >= 12) mbar_init(bars + 8 * (B_WM0 + w - 12), 1);
        asm volatile("fence.mbarrier_init.release.cluster;" ::: "memory");
        if (w >= 12) mbar_expect_tx(bars + 8 * (B_WM0 + w - 12), cta >= FIN0 ? 4096 : 8192);
        if (w >= B_CA && w < B_EA) mbar_expect_tx(bars + 8 * w, w == B_CA ? 65536 : (w == B_W2 ? 45056 : (w == B_W1 ? 32768 : 16384)));
        mbar_expect_tx(bars + 8 * (w + 16), w < 8 ? 4096 : 8192);
    }
    __syncwarp();
    asm volatile("barrier.cluster.arrive.relaxed.aligned;" ::: "memory");
    if (w < 2) {
        stx32(G + G_X1 + (cta >> 4) * 1024 + 64 * (cta & 15) + t, epoch_r & 1u);
        stx32(inbox(G, cta, w, l), epoch_r & 1u);
        stx32(G + x5own + w * A12 + l, epoch_r & 1u);
        sts32_if(sb + OFF_SM + SM_PAR * 4, __uint_as_float((epoch_r + 1u) & 1u), t == 0);
        sts32_if(sb + OFF_SM + SM_FLAG * 4, 0.f, t == 0);
        sts64_if(sb + OFF_SM + (SM_PRB + 4) * 4, 0.f, 0.f, t == 0);
    }
    const float s_row = rbf(bf_lo(c_row_r) * sigmoidf_(bf_lo(c_row_r)));

    {
        const float s = s_row;
        float v[8] = {bf_lo(wm0.x) * s, bf_hi(wm0.x) * s, bf_lo(wm0.y) * s, bf_hi(wm0.y) * s, bf_lo(wm0.z) * s, bf_hi(wm0.z) * s, bf_lo(wm0.w) * s, bf_hi(wm0.w) * s};
        const bool u16 = l & 16, u8 = l & 8;
        float a[4], b[2];
#pragma unroll
        for (int i = 0; i < 4; i++) a[i] = (u16 ? v[i + 4] : v[i]) + __shfl_xor_sync(0xffffffffu, u16 ? v[i] : v[i + 4], 16);
#pragma unroll
        for (int i = 0; i < 2; i++) b[i] = (u8 ? a[i + 2] : a[i]) + __shfl_xor_sync(0xffffffffu, u8 ? a[i] : a[i + 2], 8);
        *reinterpret_cast<float2*>(smem + OFF_P + (w * 64 + (l & 7) * 8 + ((l >> 4) & 1) * 4 + ((l >> 3) & 1) * 2) * 4) = make_float2(b[0], b[1]);
    }
    const uint32_t c_full_r = ldg16(p.c + t);
    const uint32_t xv_r = ldg16(p.x + t);
    const uint32_t bias_r = ldg16(p.b2 + 16 * (cta & 31) + (l & 15));
    bar_sync(1, 512);
    uint32_t par = __float_as_uint(sm[SM_PAR]);
    PIN(par);
    if (w < 2) {
        const float* red = reinterpret_cast<const float*>(smem + OFF_P) + t;
        float r[4];
#pragma unroll
        for (int i = 0; i < 4; i++) r[i] = (red[i * 256] + red[i * 256 + 64]) + (red[i * 256 + 128] + red[i * 256 + 192]);
        stx32(G + G_X1 + (cta >> 4) * 1024 + 64 * (cta & 15) + t, tagf((r[0] + r[1]) + (r[2] + r[3]), par));
        bar_arrive(5, 128);
    }
    const int tpos = cta >= FIN0 ? (t & ~63) + 16 * (t & 3) + ((t >> 2) & 15) : (t & ~31) + 16 * (t & 1) + (l >> 1);
    { const float cf = bf_lo(c_full_r); sts32_if(sb + OFF_SM + (SM_S + tpos) * 4, rbf(cf * sigmoidf_(cf)), true); }
    const float biasv = bf_lo(bias_r);
    asm volatile("barrier.cluster.wait.aligned;" ::: "memory");
    if (w >= 12) {
        uint32_t* line = w >= 14 ? inbox(G, cta, w & 1, 0) : G + x5own + (w & 1) * A12;
        const uint32_t done = sb + OFF_SM + (SM_PRB + 4 + ((w >> 1) & 1)) * 4;
        uint32_t best = 0xffffffffu;
#pragma unroll 1
        for (int i = 0; i < NPROBE; i++) {
            uint32_t old = 0, c0, c1;
            asm volatile("{ .reg .pred q; setp.eq.u32 q, %4, 0; mov.u32 %1, %%clock; @q atom.relaxed.gpu.global.exch.b32 %0, [%3], %5;\n"
                         "setp.eq.u32 q, %0, 0x7fc1d2e3; @q st.shared.u32 [%6], %0; mov.u32 %2, %%clock; }"
                         : "+r"(old), "=r"(c0), "=r"(c1) : "l"(line), "r"(l), "r"(par ^ 1u), "r"(sb + OFF_SM + SM_PRB * 4) : "memory");
            best = min(best, c1 - c0);
            sts32_if(done, 1.f, best < PRB_NEAR);
            if (__shfl_sync(0xffffffffu, lds32(done), 0) != 0u) break;
        }
        sts32_if(sb + OFF_SM + (SM_PRB + (w & 3)) * 4, __uint_as_float(best), l == 0);
        __syncwarp();
        mbar_arrive_if(bars + 8 * B_PRB, l == 0);
    }
    {
        const uint32_t np = par ^ 1u;
        stx32_if(G + G_X2 + cta * 128 + (t & 127), np, w < 4);
        uint32_t* Gc = G + (w & 1) * A12;
        stx128_if(Gc + G_X3 + (hd >> 4) * A18 + gr((2 * js + ((l >> 3) & 1)) * 512 + (hd & 15) * 32 + (l & 7) * 4), np, np, np, np, (w >> 1) == 2 && l < 16);
        stx128_if(Gc + G_ML + gr((split * 32 + grp * 16) * 2 + (l & 7) * 4), np, np, np, np, (w >> 1) == 2 && l >= 24);
        stx128_if(Gc + G_X6 + gr((cta >> 4) * 512 + (cta & 15) * 32 + (l & 7) * 4), np, np, np, np, (w >> 1) == 2 && l >= 16 && l < 24);
        stx128_if(Gc + x5own + l * 4, np, np, np, np, (w >> 1) == 3 && l >= 8);
        stx128_if(Gc + G_M2 + gr(32 * (cta - NFFN) + l * 4), np, np, np, np, (w >> 1) == 3 && l < 8 && cta >= NFFN && cta < NFFN + NMOD);
        stx128_if(Gc + G_X7 + gr(32 * cta + l * 4), np, np, np, np, (w >> 1) == 3 && l < 8 && cta < NFFN);
    }
    mbar_wait(bars + 8 * B_PRB);
    const uint4 prb = lds128(sb + OFF_SM + SM_PRB * 4);
    const uint32_t kx = prb.z > prb.w ? 1u : 0u;
    const uint32_t* const Gn = G + (prb.x > prb.y ? A12 : 0);
    uint32_t* const x4src = inbox(G, cta, kx, t * 2);
    delay(D_WARM + w * D_WSTEP);
#pragma unroll
    for (int q = 0; q < 4; q++) stp_if(x4src + q * A14, par ^ 1u, 0u, true);
    float wv[32];
    uint32_t redw = sb + OFF_RED + (t >> 6) * 512 + (t & 63) * 8, redr = sb + OFF_RED + (t & 127) * 4, hv = sb + OFF_SM + SM_H * 4 + (t >> 6) * 64;
    PIN(redw); PIN(redr); PIN(hv);
#define SUM8(a) (((ldsf(a) + ldsf((a) + 512)) + (ldsf((a) + 1024) + ldsf((a) + 1536))) + ((ldsf((a) + 2048) + ldsf((a) + 2560)) + (ldsf((a) + 3072) + ldsf((a) + 3584))))
    {
        uint32_t* x2dst = G + G_X2 + cta * 128 + (t & 127);
        PINP(x2dst);
        mbar_wait(bars + 8 * (B_WQ0 + (w >> 2)));

        load_cols<16, 256>(wv, sb + OFF_WA + (t >> 6) * 4096 + (t & 63) * 4);
        keep32(wv, sb, par >> 1);
        mbar_wait(bars + 8 * B_H);
        const float2 y = dot_cols<16>(wv, hv);
        sts64_if(redw, y.x, y.y, true);
        if (w < 4) {
            bar_sync(8, 512);
            stx32(x2dst, tagf(SUM8(redr), par));
            bar_arrive(9, 192);
            mbar_arrive_if(bars + 8 * B_EA, t == 0);
        } else {
            bar_arrive(8, 512);
        }
    }
    uint32_t* x3dst = G + G_X3 + (hd >> 4) * A18 + gr((2 * js + ((l >> 3) & 1)) * 512 + (hd & 15) * 32 + (l & 7) * 4) + (l >> 4) * A12;
    const uint32_t* x3src = Gn + G_X3 + grp * A18 + gr(t * 4);
    {
        const int row = t >> 2, qd = t & 3;
        uint32_t qv = sb + OFF_SM + (SM_Q + 16 * qd + (qd >> 1) * 4) * 4;
        uint32_t sdst = sb + OFF_SM + SM_STG * 4 + (row >> 6) * 128 + ((((row >> 3) & 7) ^ (hd & 7)) << 4) + (row & 7) * 2;
        PINP(x3dst); PINP(x3src); PIN(qv); PIN(sdst);
        const uint32_t rb = (ldx32(x4src) ^ ldx32(x4src + A14)) | (ldx32(x4src + 2 * A14) ^ ldx32(x4src + 3 * A14));
        mbar_wait(bars + 8 * (B_WUK0 + (w >> 2)));

#pragma unroll
        for (int i = 0; i < 4; i++) {
            const uint4 r = lds128(sb + OFF_WB + (i >> 1) * 16384 + row * 128 + (((2 * qd + (i & 1)) ^ (row & 7)) << 4));
            wv[8 * i] = bf_lo(r.x); wv[8 * i + 1] = bf_hi(r.x); wv[8 * i + 2] = bf_lo(r.y); wv[8 * i + 3] = bf_hi(r.y);
            wv[8 * i + 4] = bf_lo(r.z); wv[8 * i + 5] = bf_hi(r.z); wv[8 * i + 6] = bf_lo(r.w); wv[8 * i + 7] = bf_hi(r.w);
        }
        keep32(wv, sb, par >> 1);
        mbar_wait(bars + 8 * B_Q);
        float a4[4] = {0.f, 0.f, 0.f, 0.f};
#pragma unroll
        for (int i = 0; i < 8; i++) {
            const float4 v = ldsf4(qv + (i >> 2) * 288 + (i & 3) * 16);
            a4[0] = fmaf(v.x, wv[4 * i], a4[0]); a4[1] = fmaf(v.y, wv[4 * i + 1], a4[1]); a4[2] = fmaf(v.z, wv[4 * i + 2], a4[2]); a4[3] = fmaf(v.w, wv[4 * i + 3], a4[3]);
        }
        float y = (a4[0] + a4[1]) + (a4[2] + a4[3]);
        y += __shfl_xor_sync(0xffffffffu, y, 1);
        y += __shfl_xor_sync(0xffffffffu, y, 2);
        sts16_if(sdst, pack_bf(y * (0.08838834764831845f * 1.4426950408889634f), 0.f) + rb, qd == 0);
    }
    bar_sync(1, 512);
    const float x0 = bf_lo(xv_r) - sm[SM_MEAN];
    if (w == 0) {
        const uint4 v = lds128(sb + OFF_SM + SM_STG * 4 + (l & 15) * 16);
        stv_if(x3dst, (v.x & 0xfffefffeu) | par | (kx << 16), v.y, v.z, v.w, true);
        mbar_arrive_if(bars + 8 * B_EB, t == 0);
    }
    {
        const uint32_t* src = x3src;
        delay(D_X3);
        uint4 v0 = ldv(src), v1 = ldv(src + 2 * A14); int it = 0;
        while (any_bit0(mis2(v0.x, v1.x, par))) {
            ldv_if(v0, src, bad(v0.x, par)); ldv_if(v1, src + 2 * A14, bad(v1.x, par));
            spin_guard(it);
        }

        *reinterpret_cast<uint4*>(smem + OFF_QA + t * 16) = v0;
        *reinterpret_cast<uint4*>(smem + OFF_QA + 8192 + t * 16) = v1;
        fence_async();
    }
    const int q2 = (l & 3) * 2, r8 = l >> 2;
    const int wg = w >> 2, ww = w & 3;
    const bool u16 = l & 16, u8 = l & 8;
    const int hl = q2 + (u8 ? 1 : 0) + (u16 ? 8 : 0);
    float s[8], o[4][8];
    const uint32_t pdst = sb + OFF_P + wg * 2048 + ((l & 7) + 8 * (l >> 4)) * 128 + (((2 * ww + ((l >> 3) & 1)) ^ (l & 7)) << 4);
    const uint32_t dv = gdesc(sb + OFF_CKV + (wg & 1) * 32768), dp = gdesc(sb + OFF_P);
    uint32_t x4off[4];
#define X4_TARGETS()                                                                                                              \
    _Pragma("unroll") for (int n = 0; n < 4; n++) {                                                                               \
        const int hh = q2 + (n & 1) + 8 * (n >> 1), j = 2 * (wg & 1) + (ww >> 1);                                                 \
        x4off[n] = (uint32_t)(inbox(G, (grp * 16 + hh) * 4 + j, lds32(sb + OFF_QA + j * 4096 + hh * 128) >> 16, split * 64 + ((ww & 1) * 8 + r8) * 4) - G); \
        PIN(x4off[n]);                                                                                                            \
    }
#define WRITE_P(m0, m1, m2, m3)                                                                                                   \
    const uint32_t p0 = pack_bf(ex2(s[0] - (m0)), ex2(s[1] - (m1))), p1 = pack_bf(ex2(s[2] - (m0)), ex2(s[3] - (m1)));            \
    const uint32_t p2 = pack_bf(ex2(s[4] - (m2)), ex2(s[5] - (m3))), p3 = pack_bf(ex2(s[6] - (m2)), ex2(s[7] - (m3)));            \
    asm volatile("stmatrix.sync.aligned.m8n8.x4.trans.shared.b16 [%0], {%1,%2,%3,%4};" :: "r"(pdst), "r"(p0), "r"(p1), "r"(p2), "r"(p3) : "memory"); \
    fence_async();
#define ROW_SUMS()                                                                                                                \
    {                                                                                                                             \
        const float m0 = bf_lo(p0) + bf_lo(p1), m1 = bf_hi(p0) + bf_hi(p1), m2 = bf_lo(p2) + bf_lo(p3), m3 = bf_hi(p2) + bf_hi(p3); \
        const float a0 = (u16 ? m2 : m0) + __shfl_xor_sync(0xffffffffu, u16 ? m0 : m2, 16);                                       \
        const float a1 = (u16 ? m3 : m1) + __shfl_xor_sync(0xffffffffu, u16 ? m1 : m3, 16);                                       \
        float r = (u8 ? a1 : a0) + __shfl_xor_sync(0xffffffffu, u8 ? a0 : a1, 8);                                                 \
        r += __shfl_xor_sync(0xffffffffu, r, 4);                                                                                  \
        sts32_if(sb + OFF_SM + (SM_SUMA + hl * 8 + w) * 4, r, !(l & 4));                                                          \
    }
#define PV_CHUNK(ch, first)                                                                                                       \
    wg_fence();                                                                                                                   \
    _Pragma("unroll") for (int i = 0; i < 4; i++) wgmma16<1, first ? 0 : 1>(o[i], dv + (ch) * 4096 + i * 512, dp + (ch) * 128);   \
    _Pragma("unroll") for (int k = 1; k < 4; k++)                                                                                 \
        _Pragma("unroll") for (int i = 0; i < 4; i++) wgmma16<1, 1>(o[i], dv + (ch) * 4096 + i * 512 + k * 128, dp + (ch) * 128 + k * 2); \
    wg_commit();
#define PUBLISH_O()                                                                                                               \
    _Pragma("unroll") for (int n = 0; n < 4; n++) {                                                                               \
        const int a = (n & 1) + 4 * (n >> 1);                                                                                     \
        stv_if(G + x4off[n], tagu(pack_bf(o[0][a], o[0][a + 2]), par), pack_bf(o[1][a], o[1][a + 2]), \
               tagu(pack_bf(o[2][a], o[2][a + 2]), par), pack_bf(o[3][a], o[3][a + 2]), true);                                               \
    }
#define PUBLISH_ML(ref)                                                                                                           \
    stp_if(G + G_ML + gr((split * 32 + grp * 16 + hl) * 2) + ((l >> 2) & 1) * A12, tagf(ref, par),                                                           \
           __float_as_uint(sum4(ldsf4(sb + OFF_SM + (SM_SUMA + hl * 8) * 4)) + sum4(ldsf4(sb + OFF_SM + (SM_SUMA + hl * 8 + 4) * 4))), true);
    if (w < 8) {
        const uint32_t da = gdesc(sb + OFF_CKV + wg * 65536), db = gdesc(sb + OFF_QA);
        bar_sync(15, 512);

        if (wg == 1) delay(D_SB);
#pragma unroll
        for (int g = 0; g < 4; g++) {
            mbar_wait(bars + 8 * (wg == 0 ? B_CA : B_CB0 + g));
            wg_fence();
            if (g == 0) wgmma16<0, 0>(s, da, db); else wgmma16<0, 1>(s, da + g * 1024, db + g * 256);
#pragma unroll
            for (int i = 8 * g + 1; i < 8 * g + 8; i++) wgmma16<0, 1>(s, da + (i >> 2) * 512 + (i & 3) * 2, db + (i >> 2) * 128 + (i & 3) * 2);
            wg_commit();
        }
        wg_wait0();
        const float amax = fmaxf(fmaxf(fmaxf(fabsf(s[0]), fabsf(s[1])), fmaxf(fabsf(s[2]), fabsf(s[3]))), fmaxf(fmaxf(fabsf(s[4]), fabsf(s[5])), fmaxf(fabsf(s[6]), fabsf(s[7]))));
        sts32_if(sb + OFF_SM + SM_FLAG * 4, 1.f, amax > FAST_RANGE);
        WRITE_P(0.f, 0.f, 0.f, 0.f)
        if (wg == 0) bar_arrive(4, 384); else bar_arrive(5, 384);
        if (par < 2u) ROW_SUMS()
        if (wg == 0) {
            bar_arrive(6, 160);
        } else {
            if (ww == 0) {
                bar_sync(11, 128);
                bar_sync(6, 160);
                if (sm[SM_FLAG] == 0.f) { PUBLISH_ML(0.f) }
            } else {
                bar_arrive(11, 128);
            }
        }
        bar_sync(10, 512);
    } else {
        bar_arrive(15, 512);
        bar_sync(4, 384);
        PV_CHUNK(0, true)
        X4_TARGETS()

        bar_sync(5, 384);
        const float flag = sm[SM_FLAG];
        PV_CHUNK(1, false)
        wg_wait0();

        if (flag == 0.f) {
            PUBLISH_O()
            mbar_arrive_if(bars + 8 * B_EC, l == 0);
        }
        bar_arrive(10, 512);
    }
    if (sm[SM_FLAG] != 0.f) {
        float mx[4];
        if (w < 8) {
            const float m0 = fmaxf(s[0], s[2]), m1 = fmaxf(s[1], s[3]), m2 = fmaxf(s[4], s[6]), m3 = fmaxf(s[5], s[7]);
            const float a0 = fmaxf(u16 ? m2 : m0, __shfl_xor_sync(0xffffffffu, u16 ? m0 : m2, 16));
            const float a1 = fmaxf(u16 ? m3 : m1, __shfl_xor_sync(0xffffffffu, u16 ? m1 : m3, 16));
            float r = fmaxf(u8 ? a1 : a0, __shfl_xor_sync(0xffffffffu, u8 ? a0 : a1, 8));
            r = fmaxf(r, __shfl_xor_sync(0xffffffffu, r, 4));
            sts32_if(sb + OFF_SM + (SM_MAXA + hl * 8 + w) * 4, r, !(l & 4));
        }
        bar_sync(12, 512);
        if (w < 8) {
#pragma unroll
            for (int i = 0; i < 4; i++) {
                const uint32_t a = sb + OFF_SM + (SM_MAXA + (q2 + (i & 1) + 8 * (i >> 1)) * 8) * 4;
                const float4 u = ldsf4(a), v = ldsf4(a + 16);
                mx[i] = fmaxf(fmaxf(fmaxf(u.x, u.y), fmaxf(u.z, u.w)), fmaxf(fmaxf(v.x, v.y), fmaxf(v.z, v.w)));
                mx[i] = __uint_as_float(tagf(mx[i], par));
            }
            WRITE_P(mx[0], mx[1], mx[2], mx[3])
            ROW_SUMS()
        }
        bar_sync(12, 512);
        if (w == 4) { PUBLISH_ML(u16 ? (u8 ? mx[3] : mx[2]) : (u8 ? mx[1] : mx[0])) }
        if (w >= 8) {
            PV_CHUNK(0, true)
            PV_CHUNK(1, false)
            wg_wait0();
            PUBLISH_O()
            mbar_arrive_if(bars + 8 * B_EC, l == 0);
        }
        bar_sync(12, 512);
    }

    const uint32_t lt = sb + OFF_LATE;
    {
        const uint32_t* mls = Gn + G_ML + (l & 3) * A14 + w * 64 + hd * 2;
        uint32_t cpd = sb + OFF_QA + (w * 134 + 64 * (l & 1) + 16 * (l >> 4) + ((l >> 1) & 7)) * 4;
        uint32_t psrc = sb + OFF_QA + ((l >> 4) * 8 * 134 + 16 * (w >> 1) + (l & 15)) * 4;
        uint32_t* x5dst = G + x5own + (t & 127);
        PINP(mls); PIN(cpd); PIN(psrc); PINP(x5dst);
        const unsigned tx4 = clk();
        const bool have_wuv = mbar_test(bars + 8 * (B_WUV0 + (w >> 2)));
        if (have_wuv) { load_cols<16, 256>(wv, sb + OFF_WA + (t >> 6) * 4096 + (t & 63) * 4); keep32(wv, sb, par >> 1); }
        while ((int)(clk() - tx4) < D_X4) { }

        uint2 v0 = ldp(x4src), v1 = ldp(x4src + A14), v2 = ldp(x4src + 2 * A14), v3 = ldp(x4src + 3 * A14), ml = ldp(mls); int it = 0;
        while (any_bit0(or3(mis2(v0.x, v1.x, par), mis2(v2.x, v3.x, par), ml.x ^ par))) {
            ldp_if(v0, x4src, bad(v0.x, par)); ldp_if(v1, x4src + A14, bad(v1.x, par)); ldp_if(v2, x4src + 2 * A14, bad(v2.x, par)); ldp_if(v3, x4src + 3 * A14, bad(v3.x, par));
            ldp_if(ml, mls, bad(ml.x, par));
            spin_guard(it);
        }

        float a0, a1, a2, a3, lw = __uint_as_float(ml.y), mw = 0.f;
        if (__any_sync(0xffffffffu, ml.x > 1u)) {
            mw = fmaxf(__uint_as_float(ml.x), __shfl_xor_sync(0xffffffffu, __uint_as_float(ml.x), 1));
            mw = fmaxf(mw, __shfl_xor_sync(0xffffffffu, mw, 2));
            const float f = ex2(__uint_as_float(ml.x) - mw);
            const float f0 = __shfl_sync(0xffffffffu, f, 0), f1 = __shfl_sync(0xffffffffu, f, 1), f2 = __shfl_sync(0xffffffffu, f, 2), f3 = __shfl_sync(0xffffffffu, f, 3);
            a0 = (f0 * bf_lo(v0.x) + f1 * bf_lo(v1.x)) + (f2 * bf_lo(v2.x) + f3 * bf_lo(v3.x)); a1 = (f0 * bf_hi(v0.x) + f1 * bf_hi(v1.x)) + (f2 * bf_hi(v2.x) + f3 * bf_hi(v3.x));
            a2 = (f0 * bf_lo(v0.y) + f1 * bf_lo(v1.y)) + (f2 * bf_lo(v2.y) + f3 * bf_lo(v3.y)); a3 = (f0 * bf_hi(v0.y) + f1 * bf_hi(v1.y)) + (f2 * bf_hi(v2.y) + f3 * bf_hi(v3.y));
            lw *= f;
        } else {
            a0 = (bf_lo(v0.x) + bf_lo(v1.x)) + (bf_lo(v2.x) + bf_lo(v3.x)); a1 = (bf_hi(v0.x) + bf_hi(v1.x)) + (bf_hi(v2.x) + bf_hi(v3.x));
            a2 = (bf_lo(v0.y) + bf_lo(v1.y)) + (bf_lo(v2.y) + bf_lo(v3.y)); a3 = (bf_hi(v0.y) + bf_hi(v1.y)) + (bf_hi(v2.y) + bf_hi(v3.y));
        }
        sts32_if(cpd, a0, true); sts32_if(cpd + 32, a1, true); sts32_if(cpd + 128, a2, true); sts32_if(cpd + 160, a3, true);
        sts32_if(sb + OFF_SM + (SM_W + (l < 4 ? 16 + 4 * w + l : w)) * 4, l < 4 ? lw : mw, l < 5);
        if (!have_wuv) {
            mbar_wait(bars + 8 * (B_WUV0 + (w >> 2)));
            load_cols<16, 256>(wv, sb + OFF_WA + (t >> 6) * 4096 + (t & 63) * 4);
            keep32(wv, sb, par >> 1);
        }

        bar_sync(3, 544);
        const float ref = ldsf(sb + OFF_SM + (SM_W + (l & 15)) * 4);
        float c = ((ldsf(psrc) + ldsf(psrc + 536)) + (ldsf(psrc + 1072) + ldsf(psrc + 1608))) + ((ldsf(psrc + 2144) + ldsf(psrc + 2680)) + (ldsf(psrc + 3216) + ldsf(psrc + 3752)));
        if (__any_sync(0xffffffffu, ref != 0.f)) {
            float M = ref;
#pragma unroll
            for (int o = 8; o; o >>= 1) M = fmaxf(M, __shfl_xor_sync(0xffffffffu, M, o));
            const float f = ex2(ref - M);
            c = 0.f;
#pragma unroll 1
            for (int i = 0; i < 8; i++) c = fmaf(__shfl_sync(0xffffffffu, f, (l >> 4) * 8 + i), ldsf(psrc + 536 * i), c);
        }
        c += __shfl_xor_sync(0xffffffffu, c, 16);
        sts32_if(sb + OFF_SM + (SM_H + 16 * (w >> 1) + (l & 15)) * 4 + (w & 1) * 512, c, !u16);
        __syncwarp();
        const float2 y = dot_cols<16>(wv, hv + (w & 1) * 512);
        sts64_if(redw, y.x, y.y, true);

        if (w < 4) {
            bar_sync(8, 544);
            const uint32_t r = tagf(SUM8(redr) * sm[SM_W + 80], par);
            stx32(x5dst, r); stx32(x5dst + A12, r);
        } else {
            bar_arrive(8, 544);
        }
    }
    const uint32_t col16 = 2 * (l & 7) + (l >> 4);
    const uint32_t* m2 = Gn + G_M2 + t;
    uint32_t ga = par, sbv = par, cbv = par;
    bool mod_todo = cta >= NFFN && cta < NFFN + NMOD;
    {
        const uint32_t* src = Gn + G_X5 + gr((cta >> 4) * 512 + t);
        uint32_t dst = sb + OFF_P + ((2 * (l & 15) + (l >> 4)) * 20 + w) * 4, wsrc = sb + OFF_WB + w * 2048 + l * 4;
        uint32_t* x6dst = G + G_X6 + gr((cta >> 4) * 512 + (cta & 15) * 32 + l);
        uint32_t vdst = lt + (LT_V + 32 * w + 16 * (l & 1) + (l >> 1)) * 4, vsrc = lt + (LT_V + 32 * w + 16 * (l >> 4)) * 4;
        PINP(src); PIN(dst); PIN(wsrc); PINP(x6dst); PIN(vdst); PIN(vsrc);
        const unsigned tx5 = clk();
#define HALF_SUM(v_) ((u16 ? (v_).y : (v_).x) + __shfl_xor_sync(0xffffffffu, u16 ? (v_).x : (v_).y, 16))
#define MOD_PART()                                                                                         \
        {                                                                                                  \
            load_cols<16, 128>(wv, sb + OFF_WM2 + w * 2048 + l * 4);                                       \
            const float2 ym = dot_cols<16>(wv, sb + OFF_SM + (SM_S + 32 * w + 16 * (l >> 4)) * 4);         \
            sts32_if(lt + (LT_FZ + (2 * (l & 15) + (l >> 4)) * 20 + w) * 4, HALF_SUM(ym), true);           \
            bar_arrive(7, 544);                                                                            \
        }
        if (mod_todo && mbar_test(bars + 8 * (B_WM0 + (w >> 2)))) { MOD_PART() mod_todo = false; }
        const bool have_wo = mbar_test(bars + 8 * (B_WO0 + (w >> 1)));
        if (have_wo) { load_cols<16, 128>(wv, wsrc); keep32(wv, sb, par >> 1); }
        while ((int)(clk() - tx5) < D_X5) { }

        uint32_t a0 = ldx32(src), a1 = ldx32(src + A18), a2 = ldx32(src + A20), a3 = ldx32(src + A18 + A20); int it = 0;
        if (cta < NFFN) { ga = ldx32(m2); sbv = ldx32(m2 + 512); cbv = ldx32(m2 + A14); }
        while (any_bit0(or3(mis2(a0, a1, par), mis2(a2, a3, par), 0u))) {
            ldx32_if(a0, src, bad(a0, par)); ldx32_if(a1, src + A18, bad(a1, par)); ldx32_if(a2, src + A20, bad(a2, par)); ldx32_if(a3, src + A18 + A20, bad(a3, par));
            spin_guard(it);
        }
        sts32_if(vdst, (__uint_as_float(a0) + __uint_as_float(a1)) + (__uint_as_float(a2) + __uint_as_float(a3)), true);

        __syncwarp();
        float4 cv[4];
#pragma unroll
        for (int q = 0; q < 4; q++) cv[q] = ldsf4(vsrc + 16 * q);
        if (!have_wo) {
            mbar_wait(bars + 8 * (B_WO0 + (w >> 1)));
            load_cols<16, 128>(wv, wsrc);
        }

        float b0 = 0.f, b1 = 0.f, c0 = 0.f, c1 = 0.f;
#pragma unroll
        for (int q = 0; q < 4; q++) {
            b0 = fmaf(cv[q].x, wv[8 * q], b0); c0 = fmaf(cv[q].x, wv[8 * q + 1], c0); b1 = fmaf(cv[q].y, wv[8 * q + 2], b1); c1 = fmaf(cv[q].y, wv[8 * q + 3], c1);
            b0 = fmaf(cv[q].z, wv[8 * q + 4], b0); c0 = fmaf(cv[q].z, wv[8 * q + 5], c0); b1 = fmaf(cv[q].w, wv[8 * q + 6], b1); c1 = fmaf(cv[q].w, wv[8 * q + 7], c1);
        }
        b0 += b1; c0 += c1;
        sts32_if(dst, ((l & 16) ? c0 : b0) + __shfl_xor_sync(0xffffffffu, (l & 16) ? b0 : c0, 16), true);
        if (w == 15) {
            bar_sync(13, 512);
            const uint32_t r = sb + OFF_P + l * 80;
            const uint32_t v = tagf((sum4(ldsf4(r)) + sum4(ldsf4(r + 16))) + (sum4(ldsf4(r + 32)) + sum4(ldsf4(r + 48))), par);
            stx32(x6dst, v); stx32(x6dst + A12, v);
        } else {
            bar_arrive(13, 512);
        }
    }
    if (mod_todo) { mbar_wait(bars + 8 * (B_WM0 + (w >> 2))); MOD_PART() }

    if (cta < NFFN) {
        const unsigned tp6 = clk();
        int it = 0;
        while (any_bit0(or3(mis2(ga, sbv, par), cbv ^ par, 0u))) {
            ldx32_if(ga, m2, bad(ga, par)); ldx32_if(sbv, m2 + 512, bad(sbv, par)); ldx32_if(cbv, m2 + A14, bad(cbv, par));
            spin_guard(it);
        }
        const float cb1 = 1.f + __uint_as_float(cbv);
        uint32_t vw = lt + (LT_Y + tpos) * 4, vr = lt + (LT_Y + 32 * w + 16 * (l >> 4)) * 4, fz = lt + (LT_FZ + (2 * (l & 15) + (l >> 4)) * 20 + w) * 4;
        sts32_if(vw + 2048, cb1, true);
        sts32_if(vw + 4096, __uint_as_float(sbv), true);

        const uint32_t* src = Gn + G_X6 + t;
        PINP(src); PIN(vw); PIN(vr); PIN(fz);
#define FFN_UV()                                                                             \
        {                                                                                    \
            load_cols<16, 128>(wv, sb + OFF_W1 + w * 2048 + l * 4);                          \
            __syncwarp();                                                                    \
            const float2 yu = dot_cols<16>(wv, vr + 2048), yv = dot_cols<16>(wv, vr + 4096); \
            sts32_if(fz + 2560, HALF_SUM(yu), true);                                         \
            sts32_if(fz + 5120, HALF_SUM(yv), true);                                         \
            bar_arrive(7, 544);                                                              \
        }
        const bool have_w1 = mbar_test(bars + 8 * B_W1);
        if (have_w1) FFN_UV()
        uint32_t x6[8];
        while ((int)(clk() - tp6) < D_X6) { }

#pragma unroll
        for (int i = 0; i < 8; i++) x6[i] = ldx32(src + gr(i * 512));
        if (!have_w1) { mbar_wait(bars + 8 * B_W1); FFN_UV() }

        while (any_bit0(or3(or3(mis2(x6[0], x6[1], par), mis2(x6[2], x6[3], par), mis2(x6[4], x6[5], par)), mis2(x6[6], x6[7], par), 0u))) {
#pragma unroll
            for (int i = 0; i < 8; i++) ldx32_if(x6[i], src + gr(i * 512), bad(x6[i], par));
            spin_guard(it);
        }
        const float xs = x0 + __uint_as_float(ga) * (((__uint_as_float(x6[0]) + __uint_as_float(x6[1])) + (__uint_as_float(x6[2]) + __uint_as_float(x6[3]))) +
                                                     ((__uint_as_float(x6[4]) + __uint_as_float(x6[5])) + (__uint_as_float(x6[6]) + __uint_as_float(x6[7]))));

        sts32_if(vw, xs * cb1, true);
        __syncwarp();
        const float2 y = dot_cols<16>(wv, vr);
        const float sq = xs * xs;
        float r = ((l & 1) ? sq : xs) + __shfl_xor_sync(0xffffffffu, (l & 1) ? xs : sq, 1);
#pragma unroll
        for (int o = 2; o <= 16; o <<= 1) r += __shfl_xor_sync(0xffffffffu, r, o);
        sts32_if(fz, HALF_SUM(y), true);
        sts32_if(lt + (LT_ST + l * 16 + w) * 4, r, l < 2);
        bar_arrive(14, 544);
        stx32_if(G + G_EPOCH + l * 32, par, cta == 0 && w == 0);
    } else if (cta >= FIN0) {
        const int k = cta - FIN0;
        int it = 0;
        const unsigned tp6 = clk();
        float base = 0.f;
        if (w == 15) {
            const uint32_t* s6 = Gn + G_X6 + gr((l >> 4) * 512 + 16 * k + (l & 15));
            const uint32_t* sg = Gn + G_M2 + 16 * k + (l & 15);
            const uint32_t xr = ldg16(p.x + 16 * k + (l & 15));
            while ((int)(clk() - tp6) < D_X6) { }
            uint32_t a0 = ldx32(s6), a1 = ldx32(s6 + A14), a2 = ldx32(s6 + 2 * A14), a3 = ldx32(s6 + 3 * A14), g1 = ldx32(sg);
            while (any_bit0(or3(mis2(a0, a1, par), mis2(a2, a3, par), g1 ^ par))) {
                ldx32_if(a0, s6, bad(a0, par)); ldx32_if(a1, s6 + A14, bad(a1, par)); ldx32_if(a2, s6 + 2 * A14, bad(a2, par)); ldx32_if(a3, s6 + 3 * A14, bad(a3, par));
                ldx32_if(g1, sg, bad(g1, par));
                spin_guard(it);
            }
            float r = (__uint_as_float(a0) + __uint_as_float(a1)) + (__uint_as_float(a2) + __uint_as_float(a3));
            r += __shfl_xor_sync(0xffffffffu, r, 16);
            base = bf_lo(xr) + __uint_as_float(g1) * r;
        }
        const uint32_t* src = Gn + G_X7 + gr(min(88 * w + 4 * min(l, 21), 1372));
        uint32_t hw = sb + OFF_QA + (144 * w + l) * 4, hr = sb + OFF_QA + (144 * w + 36 * (l >> 3)) * 4, pd = sb + OFF_P + (col16 * 20 + w) * 4;
        __nv_bfloat16* outp = p.out + 16 * k + (l & 15);
        PINP(src); PIN(hw); PIN(hr); PIN(pd); PINP(outp);
        float w2v[44];
        mbar_wait(bars + 8 * B_W2);
        {
            uint32_t raw[22];
#pragma unroll
            for (int i = 0; i < 22; i++) raw[i] = lds32(sb + OFF_W2 + w * 2816 + i * 128 + l * 4);
#pragma unroll
            for (int i = 0; i < 22; i++) { w2v[2 * i] = bf_lo(raw[i]); w2v[2 * i + 1] = bf_hi(raw[i]); }
#pragma unroll
            for (int i = 0; i < 44; i += 4)
                asm volatile("{ .reg .pred q; setp.ne.u32 q, %5, 0; @q st.shared.v4.f32 [%0], {%1,%2,%3,%4}; }" :: "r"(sb), "f"(w2v[i]), "f"(w2v[i + 1]), "f"(w2v[i + 2]), "f"(w2v[i + 3]), "r"(par >> 1) : "memory");
        }
        while ((int)(clk() - tp6) < D_X8) { }

        uint4 v = ldx128(src);
        while (any_bit0(or3(mis2(v.x, v.y, par), mis2(v.z, v.w, par), 0u))) { v = ldx128(src); spin_guard(it); }

        sts32_if(hw, __uint_as_float(v.x), true); sts32_if(hw + 144, __uint_as_float(v.y), true);
        sts32_if(hw + 288, __uint_as_float(v.z), true); sts32_if(hw + 432, __uint_as_float(v.w), true);
        __syncwarp();
        float a0 = 0.f, a1 = 0.f, b0 = 0.f, b1 = 0.f;
#pragma unroll
        for (int q = 0; q < 6; q++) {
            const float4 h = ldsf4(hr + 16 * q);
            a0 = fmaf(h.x, w2v[8 * q], a0); b0 = fmaf(h.x, w2v[8 * q + 1], b0); a1 = fmaf(h.y, w2v[8 * q + 2], a1); b1 = fmaf(h.y, w2v[8 * q + 3], b1);
            if (q < 5) { a0 = fmaf(h.z, w2v[8 * q + 4], a0); b0 = fmaf(h.z, w2v[8 * q + 5], b0); a1 = fmaf(h.w, w2v[8 * q + 6], a1); b1 = fmaf(h.w, w2v[8 * q + 7], b1); }
        }
        sts32_if(pd, reduce16(make_float2(a0 + a1, b0 + b1), l), !(l & 8));
        if (w == 15) {
            bar_sync(4, 544);
            const uint32_t r = sb + OFF_P + ((l & 15) * 20 + (l >> 4) * 8) * 4;
            float o = sum4(ldsf4(r)) + sum4(ldsf4(r + 16));
            const float gbv = ldsf(lt + (LT_R2 + (l & 15)) * 4);
            o += __shfl_xor_sync(0xffffffffu, o, 16);
            asm volatile("{ .reg .pred q; .reg .b16 h; setp.ne.u32 q, %2, 0; cvt.u16.u32 h, %1; @q st.global.u16 [%0], h; }"
                         :: "l"(outp), "r"(pack_bf(base + gbv * (o + biasv), 0.f)), "r"((uint32_t)(l < 16)) : "memory");
        } else {
            bar_arrive(4, 544);
        }
    }
}

typedef CUresult (*EncodeFn)(CUtensorMap*, CUtensorMapDataType, cuuint32_t, void*, const cuuint64_t*, const cuuint64_t*, const cuuint32_t*,
                             const cuuint32_t*, CUtensorMapInterleave, CUtensorMapSwizzle, CUtensorMapL2promotion, CUtensorMapFloatOOBfill);

void make_map(EncodeFn enc, CUtensorMap* m, const void* base, int rank, const cuuint64_t* dims, const cuuint64_t* strides, const cuuint32_t* box,
              CUtensorMapSwizzle sw, CUtensorMapL2promotion promo) {
    const cuuint32_t es[3] = {1, 1, 1};
    enc(m, CU_TENSOR_MAP_DATA_TYPE_BFLOAT16, rank, const_cast<void*>(base), dims, strides, box, es, CU_TENSOR_MAP_INTERLEAVE_NONE, sw, promo,
        CU_TENSOR_MAP_FLOAT_OOB_FILL_NONE);
}
}

extern "C" void kernel_launch(void* const* d_in, const int* in_sizes, int n_in, void* d_out, int out_size) {
    (void)in_sizes; (void)n_in; (void)out_size;
    static EncodeFn enc = nullptr;
    static void* scratch = nullptr;
    if (!enc) {
        cudaGetSymbolAddress(&scratch, g_scratch);
        void* fn = nullptr;
        cudaDriverEntryPointQueryResult qr;
        cudaGetDriverEntryPoint("cuTensorMapEncodeTiled", &fn, cudaEnableDefault, &qr);
        enc = (EncodeFn)fn;
        cudaFuncSetAttribute(fused_decode_kernel, cudaFuncAttributeMaxDynamicSharedMemorySize, SMEM_BYTES);
    }
    CUtensorMap m_wq, m_wuk, m_ckv, m_wuv, m_wo, m_wm, m_w1, m_w2, m_gb;
    {
        const cuuint64_t d[2] = {4096, 512}, s[1] = {8192};
        const cuuint32_t b[2] = {64, 32}, bq[2] = {128, 16};
        make_map(enc, &m_wq, d_in[2], 2, d, s, bq, CU_TENSOR_MAP_SWIZZLE_NONE, CU_TENSOR_MAP_L2_PROMOTION_L2_128B);
        make_map(enc, &m_wuk, d_in[3], 2, d, s, b, CU_TENSOR_MAP_SWIZZLE_128B, CU_TENSOR_MAP_L2_PROMOTION_L2_128B);
    }
    {
        const cuuint64_t d[3] = {4096, 64, 8}, s[2] = {8192, 8192 * 64};
        const cuuint32_t b[3] = {128, 16, 1};
        make_map(enc, &m_wuv, d_in[4], 3, d, s, b, CU_TENSOR_MAP_SWIZZLE_NONE, CU_TENSOR_MAP_L2_PROMOTION_L2_128B);
    }
    {
        const cuuint64_t d[2] = {512, 8192}, s[1] = {1024};
        const cuuint32_t b[2] = {64, 32};
        make_map(enc, &m_ckv, d_in[1], 2, d, s, b, CU_TENSOR_MAP_SWIZZLE_128B, CU_TENSOR_MAP_L2_PROMOTION_L2_128B);
    }
    {
        const cuuint64_t d[2] = {512, 4096}, s[1] = {1024};
        const cuuint32_t b[2] = {32, 64};
        make_map(enc, &m_wo, d_in[5], 2, d, s, b, CU_TENSOR_MAP_SWIZZLE_NONE, NARROW_PROMO);
    }
    {
        const cuuint64_t d[2] = {3072, 512}, s[1] = {6144};
        const cuuint32_t b[2] = {32, 64}, bg[2] = {16, 128};
        make_map(enc, &m_wm, d_in[12], 2, d, s, b, CU_TENSOR_MAP_SWIZZLE_NONE, NARROW_PROMO);
        make_map(enc, &m_gb, d_in[12], 2, d, s, bg, CU_TENSOR_MAP_SWIZZLE_NONE, NARROW_PROMO);
    }
    {
        const cuuint64_t d[2] = {1376, 512}, s[1] = {2752};
        const cuuint32_t b[2] = {32, 64};
        make_map(enc, &m_w1, d_in[7], 2, d, s, b, CU_TENSOR_MAP_SWIZZLE_NONE, NARROW_PROMO);
    }
    {
        const cuuint64_t d[2] = {512, 1376}, s[1] = {1024};
        const cuuint32_t b[2] = {16, 128};
        make_map(enc, &m_w2, d_in[9], 2, d, s, b, CU_TENSOR_MAP_SWIZZLE_NONE, NARROW_PROMO);
    }
    Params p;
    p.x = (const __nv_bfloat16*)d_in[0];
    p.c = (const __nv_bfloat16*)d_in[11];
    p.wmod = (const __nv_bfloat16*)d_in[12];
    p.b1 = (const __nv_bfloat16*)d_in[8];
    p.b2 = (const __nv_bfloat16*)d_in[10];
    p.out = (__nv_bfloat16*)d_out;
    p.g = (uint32_t*)(((uintptr_t)scratch + 2097151) & ~(uintptr_t)2097151);
    p.ckv = (const __nv_bfloat16*)d_in[1];
    p.wuk = (const __nv_bfloat16*)d_in[3];
    p.wuv = (const __nv_bfloat16*)d_in[4];
    p.wo = (const __nv_bfloat16*)d_in[5];
    p.w1 = (const __nv_bfloat16*)d_in[7];
    p.w2 = (const __nv_bfloat16*)d_in[9];
    fused_decode_kernel<<<NCTA, NTHR, SMEM_BYTES>>>(p, m_wq, m_wuk, m_ckv, m_wuv, m_wo, m_wm, m_w1, m_w2, m_gb);
}
```
